```python
import torch

def _softmax(x, axis=-1):
    return torch.softmax(x, dim=axis)

def _gelu(x):
    return torch.nn.functional.gelu(x, approximate='tanh')

def _silu(x):
    return torch.nn.functional.silu(x)

def _sigmoid(x):
    return torch.sigmoid(x)

def _layernorm(x, axis=-1, eps=1e-05):
    m = x.mean(dim=axis, keepdim=True)
    v = x.var(dim=axis, keepdim=True, unbiased=False)
    return (x - m) / torch.sqrt(v + eps)

def _scatter_add(tgt, idx, src, axis=0):
    return tgt.clone().index_add_(axis, idx, src)

def _segment_sum(src, seg, n):
    out = torch.zeros((n,) + src.shape[1:], dtype=src.dtype)
    return out.index_add_(0, seg, src)

def _pad(x, pw):
    flat = tuple((v for pair in reversed(pw) for v in pair))
    return torch.nn.functional.pad(x, flat)
kernel_name = 'standalone__kv_cache_quant_pre_rope_vs_post_rope__prompt'

def setup_inputs():

    _w = lambda a: (lambda t: t.to(torch.bfloat16) if t.is_floating_point() else t)(torch.as_tensor(a))
    B, Sq, Skv = (1, 2048, 2048)
    H, Dh0 = (8, 128)
    G = 64 if 64 > 0 else Dh0
    G = max(2, G // 2 * 2)
    Dh = max(G, Dh0 // G * G)
    Skv = max(Skv, Sq)
    ng = Dh // G
    bits = 3 if 3 > 1 else 4
    bits = max(2, min(8, bits))
    qmax = (1 << bits) - 1
    half = Dh // 2
    inv = 1.0 / 10000.0 ** (torch.arange(half) / max(1, half))
    ang_k = torch.arange(Skv)[:, None] * inv[None, :]
    ang_q = torch.arange(Skv - Sq, Skv)[:, None] * inv[None, :]
    kc = torch.cat([torch.cos(ang_k), torch.cos(ang_k)], dim=-1)
    ks = torch.cat([torch.sin(ang_k), torch.sin(ang_k)], dim=-1)
    qc = torch.cat([torch.cos(ang_q), torch.cos(ang_q)], dim=-1)
    qs = torch.cat([torch.sin(ang_q), torch.sin(ang_q)], dim=-1)
    qk_i = torch.randint(0, qmax + 1, (B, H, Skv, Dh)).to(torch.int32)
    qv_i = torch.randint(0, qmax + 1, (B, H, Skv, Dh)).to(torch.int32)
    ksc = torch.abs((lambda *s: torch.randn(*s, dtype=torch.bfloat16) * 0.4)(B, H, Skv, ng)) * 0.1 + 0.01
    kzp = torch.full((B, H, Skv, ng), qmax / 2.0)
    vsc = torch.abs((lambda *s: torch.randn(*s, dtype=torch.bfloat16) * 0.4)(B, H, Skv, ng)) * 0.1 + 0.01
    vzp = torch.full((B, H, Skv, ng), qmax / 2.0)
    return {'q': _w((lambda *s: torch.randn(*s, dtype=torch.bfloat16) * 6.4)(B, H, Sq, Dh) * 0.5), 'qk': _w(qk_i), 'k_scales': _w(ksc), 'k_zeros': _w(kzp), 'qv': _w(qv_i), 'v_scales': _w(vsc), 'v_zeros': _w(vzp), 'q_cos': _w(qc), 'q_sin': _w(qs), 'k_cos': _w(kc), 'k_sin': _w(ks)}

def reference(q, qk, k_scales, k_zeros, qv, v_scales, v_zeros, q_cos, q_sin, k_cos, k_sin):
    B, H, Sq, Dh = q.shape
    ng = k_scales.shape[-1]
    G = Dh // ng
    half = Dh // 2
    ks = (lambda x, n, axis: torch.repeat_interleave(x, n, dim=axis))(k_scales, G, axis=-1)
    kz = (lambda x, n, axis: torch.repeat_interleave(x, n, dim=axis))(k_zeros, G, axis=-1)
    k = ((lambda x, dt: x.to(dt))(qk, q.dtype) - kz) * ks
    vs = (lambda x, n, axis: torch.repeat_interleave(x, n, dim=axis))(v_scales, G, axis=-1)
    vz = (lambda x, n, axis: torch.repeat_interleave(x, n, dim=axis))(v_zeros, G, axis=-1)
    v = ((lambda x, dt: x.to(dt))(qv, q.dtype) - vz) * vs
    k1 = k[..., :half].clone()
    k2 = k[..., half:].clone()
    krh = torch.concatenate([-k2, k1], axis=-1)
    kr = k * k_cos[None, None, :, :] + krh * k_sin[None, None, :, :]
    q1 = q[..., :half].clone()
    q2 = q[..., half:].clone()
    qrh = torch.concatenate([-q2, q1], axis=-1)
    qr = q * q_cos[None, None, :, :] + qrh * q_sin[None, None, :, :]
    logits = torch.einsum('bhqd,bhkd->bhqk', qr, kr) * float(Dh) ** (-0.5)
    attn = _softmax(logits, axis=-1)
    out = torch.einsum('bhqk,bhkd->bhqd', attn, v)
    return out
```

```cpp
#include <cuda_runtime.h>
#include <cuda_bf16.h>
#include <stdint.h>

#define DEVINL __device__ __forceinline__

constexpr int H = 8, S = 2048, D = 128;
constexpr int NT = 16;
constexpr int TILE_BYTES = 32768;
constexpr int KST = 2, VST = 3;
constexpr int NTHREADS = 512;
constexpr int SPIN_LIMIT = 20000;
constexpr unsigned FLAG_INC = 16;
constexpr int NDIR = 7;
constexpr int PF2AT = 3;
constexpr int LEAD = 3;
constexpr int FSTR = 32;
constexpr int FWIN = 1;
#define CREG 200
#define PREG 56
#define LREG 56
#define STR2(x) #x
#define STR(x) STR2(x)

__device__ uint4 g_K[H * NT * (TILE_BYTES / 16)];
__device__ uint4 g_V[H * NT * (TILE_BYTES / 16)];
__device__ unsigned g_flags[H * 32 * FSTR];

DEVINL uint32_t smem_u32(const void* p) { return (uint32_t)__cvta_generic_to_shared(p); }
DEVINL void mbar_init(uint32_t bar, uint32_t cnt) {
  asm volatile("mbarrier.init.shared::cta.b64 [%0], %1;" ::"r"(bar), "r"(cnt) : "memory");
}
DEVINL void mbar_expect_tx(uint32_t bar, uint32_t bytes) {
  asm volatile("mbarrier.arrive.expect_tx.shared::cta.b64 _, [%0], %1;" ::"r"(bar), "r"(bytes) : "memory");
}
DEVINL void mbar_arrive(uint32_t bar) { asm volatile("mbarrier.arrive.shared::cta.b64 _, [%0];" ::"r"(bar) : "memory"); }
DEVINL bool mbar_try(uint32_t bar, uint32_t parity) {
  uint32_t ok;
  asm volatile("{\n.reg .pred p;\nmbarrier.try_wait.parity.shared::cta.b64 p, [%1], %2;\nselp.u32 %0, 1, 0, p;\n}"
               : "=r"(ok) : "r"(bar), "r"(parity) : "memory");
  return ok;
}
DEVINL void mbar_wait(uint32_t bar, uint32_t parity) {
  int it = 0;
  while (!mbar_try(bar, parity)) { if (++it > SPIN_LIMIT) break; }
}
DEVINL void mbar_arrive_remote(uint32_t bar, uint32_t cta) {
  asm volatile("{\n.reg .b32 ra;\nmapa.shared::cluster.u32 ra, %0, %1;\n"
               "mbarrier.arrive.shared::cluster.b64 _, [ra];\n}" ::"r"(bar), "r"(cta) : "memory");
}
DEVINL void bulk_load(uint32_t dst, const void* src, uint32_t bytes, uint32_t bar) {
  asm volatile("cp.async.bulk.shared::cluster.global.mbarrier::complete_tx::bytes [%0], [%1], %2, [%3];"
               ::"r"(dst), "l"(src), "r"(bytes), "r"(bar) : "memory");
}
DEVINL void bulk_load_mc(uint32_t dst, const void* src, uint32_t bytes, uint32_t bar, uint16_t mask) {
  asm volatile("cp.async.bulk.shared::cluster.global.mbarrier::complete_tx::bytes.multicast::cluster [%0], [%1], %2, [%3], %4;"
               ::"r"(dst), "l"(src), "r"(bytes), "r"(bar), "h"(mask) : "memory");
}
DEVINL void prefetch_l2(const void* src, uint32_t bytes) {
  asm volatile("cp.async.bulk.prefetch.L2.global [%0], %1;" ::"l"(src), "r"(bytes) : "memory");
}
DEVINL bool elect_one() {
  uint32_t ok;
  asm volatile("{\n.reg .pred p;\nelect.sync _|p, 0xffffffff;\nselp.u32 %0, 1, 0, p;\n}" : "=r"(ok));
  return ok;
}
DEVINL void cluster_sync() {
  asm volatile("barrier.cluster.arrive.relaxed.aligned;" ::: "memory");
  asm volatile("barrier.cluster.wait.aligned;" ::: "memory");
}
DEVINL void wg_fence() { asm volatile("wgmma.fence.sync.aligned;" ::: "memory"); }
DEVINL void wg_commit() { asm volatile("wgmma.commit_group.sync.aligned;" ::: "memory"); }
template <int N> DEVINL void wg_wait() { asm volatile("wgmma.wait_group.sync.aligned %0;" ::"n"(N) : "memory"); }
DEVINL void bar_sync(int id, int n) { asm volatile("bar.sync %0, %1;" ::"r"(id), "r"(n) : "memory"); }
DEVINL void bar_arrive(int id, int n) { asm volatile("bar.arrive %0, %1;" ::"r"(id), "r"(n) : "memory"); }

#define ACC32(d, o) \
 "+f"(d[o+0]),"+f"(d[o+1]),"+f"(d[o+2]),"+f"(d[o+3]),"+f"(d[o+4]),"+f"(d[o+5]),"+f"(d[o+6]),"+f"(d[o+7]), \
 "+f"(d[o+8]),"+f"(d[o+9]),"+f"(d[o+10]),"+f"(d[o+11]),"+f"(d[o+12]),"+f"(d[o+13]),"+f"(d[o+14]),"+f"(d[o+15]), \
 "+f"(d[o+16]),"+f"(d[o+17]),"+f"(d[o+18]),"+f"(d[o+19]),"+f"(d[o+20]),"+f"(d[o+21]),"+f"(d[o+22]),"+f"(d[o+23]), \
 "+f"(d[o+24]),"+f"(d[o+25]),"+f"(d[o+26]),"+f"(d[o+27]),"+f"(d[o+28]),"+f"(d[o+29]),"+f"(d[o+30]),"+f"(d[o+31])
#define ACC64(d) ACC32(d, 0), ACC32(d, 32)
#define REGS32 "{%0,%1,%2,%3,%4,%5,%6,%7,%8,%9,%10,%11,%12,%13,%14,%15,%16,%17,%18,%19,%20,%21,%22,%23,%24,%25,%26,%27,%28,%29,%30,%31}"
#define REGS64 "{%0,%1,%2,%3,%4,%5,%6,%7,%8,%9,%10,%11,%12,%13,%14,%15,%16,%17,%18,%19,%20,%21,%22,%23,%24,%25,%26,%27,%28,%29,%30,%31,%32,%33,%34,%35,%36,%37,%38,%39,%40,%41,%42,%43,%44,%45,%46,%47,%48,%49,%50,%51,%52,%53,%54,%55,%56,%57,%58,%59,%60,%61,%62,%63}"

#define OUT32(d, o) \
 "=f"(d[o+0]),"=f"(d[o+1]),"=f"(d[o+2]),"=f"(d[o+3]),"=f"(d[o+4]),"=f"(d[o+5]),"=f"(d[o+6]),"=f"(d[o+7]), \
 "=f"(d[o+8]),"=f"(d[o+9]),"=f"(d[o+10]),"=f"(d[o+11]),"=f"(d[o+12]),"=f"(d[o+13]),"=f"(d[o+14]),"=f"(d[o+15]), \
 "=f"(d[o+16]),"=f"(d[o+17]),"=f"(d[o+18]),"=f"(d[o+19]),"=f"(d[o+20]),"=f"(d[o+21]),"=f"(d[o+22]),"=f"(d[o+23]), \
 "=f"(d[o+24]),"=f"(d[o+25]),"=f"(d[o+26]),"=f"(d[o+27]),"=f"(d[o+28]),"=f"(d[o+29]),"=f"(d[o+30]),"=f"(d[o+31])
DEVINL void wgmma_ss_first(float (&d)[64], uint64_t da, uint64_t db) {
  asm volatile("wgmma.mma_async.sync.aligned.m64n128k16.f32.bf16.bf16 " REGS64 ", %64, %65, 0, 1, 1, 0, 0;\n"
               : OUT32(d, 0), OUT32(d, 32) : "l"(da), "l"(db));
}
DEVINL void wgmma_ss(float (&d)[64], uint64_t da, uint64_t db) {
  asm volatile("wgmma.mma_async.sync.aligned.m64n128k16.f32.bf16.bf16 " REGS64 ", %64, %65, 1, 1, 1, 0, 0;\n"
               : ACC64(d) : "l"(da), "l"(db));
}
DEVINL void wgmma_ss_first(float (&d)[32], uint64_t da, uint64_t db) {
  asm volatile("wgmma.mma_async.sync.aligned.m64n64k16.f32.bf16.bf16 " REGS32 ", %32, %33, 0, 1, 1, 0, 0;\n"
               : OUT32(d, 0) : "l"(da), "l"(db));
}
DEVINL void wgmma_ss(float (&d)[32], uint64_t da, uint64_t db) {
  asm volatile("wgmma.mma_async.sync.aligned.m64n64k16.f32.bf16.bf16 " REGS32 ", %32, %33, 1, 1, 1, 0, 0;\n"
               : ACC32(d, 0) : "l"(da), "l"(db));
}
DEVINL void wgmma_rs_tb(float (&d)[64], uint32_t a0, uint32_t a1, uint32_t a2, uint32_t a3, uint64_t db) {
  asm volatile("wgmma.mma_async.sync.aligned.m64n128k16.f32.bf16.bf16 " REGS64 ", {%64,%65,%66,%67}, %68, 1, 1, 1, 1;\n"
               : ACC64(d) : "r"(a0), "r"(a1), "r"(a2), "r"(a3), "l"(db));
}
DEVINL void wgmma_rs_tb(float (&d)[32], uint32_t a0, uint32_t a1, uint32_t a2, uint32_t a3, uint64_t db) {
  asm volatile("wgmma.mma_async.sync.aligned.m64n64k16.f32.bf16.bf16 " REGS32 ", {%32,%33,%34,%35}, %36, 1, 1, 1, 1;\n"
               : ACC32(d, 0) : "r"(a0), "r"(a1), "r"(a2), "r"(a3), "l"(db));
}
DEVINL uint64_t mkdesc(uint32_t addr, uint32_t lbo, uint32_t sbo) {
  return (uint64_t)((addr & 0x3FFFF) >> 4) | ((uint64_t)(lbo >> 4) << 16) | ((uint64_t)(sbo >> 4) << 32) | (1ull << 62);
}
template <int N> DEVINL void pin(float (&a)[N]) {
#pragma unroll
  for (int i = 0; i < N; i++) asm volatile("" : "+f"(a[i])::"memory");
}
template <int N> DEVINL void pin(uint32_t (&a)[N]) {
#pragma unroll
  for (int i = 0; i < N; i++) asm volatile("" : "+r"(a[i])::"memory");
}
DEVINL uint32_t bmul(uint32_t a, uint32_t b) { uint32_t d; asm("mul.rn.bf16x2 %0, %1, %2;" : "=r"(d) : "r"(a), "r"(b)); return d; }
DEVINL uint32_t badd(uint32_t a, uint32_t b) { uint32_t d; asm("add.rn.bf16x2 %0, %1, %2;" : "=r"(d) : "r"(a), "r"(b)); return d; }
DEVINL uint32_t bsub(uint32_t a, uint32_t b) { uint32_t d; asm("sub.rn.bf16x2 %0, %1, %2;" : "=r"(d) : "r"(a), "r"(b)); return d; }
DEVINL uint32_t bfma(uint32_t a, uint32_t b, uint32_t c) { uint32_t d; asm("fma.rn.bf16x2 %0, %1, %2, %3;" : "=r"(d) : "r"(a), "r"(b), "r"(c)); return d; }
DEVINL uint32_t dup_lo(uint32_t x) { uint32_t d; asm("{.reg .b16 a, b; mov.b32 {a, b}, %1; mov.b32 %0, {a, a};}" : "=r"(d) : "r"(x)); return d; }
DEVINL uint32_t dup_hi(uint32_t x) { uint32_t d; asm("{.reg .b16 a, b; mov.b32 {a, b}, %1; mov.b32 %0, {b, b};}" : "=r"(d) : "r"(x)); return d; }
DEVINL uint32_t bscale(uint32_t x) { return bfma(x, 0x3E033E03u, bmul(x, 0xB9D8B9D8u)); }
DEVINL uint32_t bmaxabs(uint32_t a, uint32_t b) { uint32_t d; asm("max.NaN.xorsign.abs.bf16x2 %0, %1, %2;" : "=r"(d) : "r"(a), "r"(b)); return d; }
DEVINL uint32_t pack_bf16(float lo, float hi) { uint32_t d; asm("cvt.rn.bf16x2.f32 %0, %1, %2;" : "=r"(d) : "f"(hi), "f"(lo)); return d; }
DEVINL uint32_t i2bf2(int lo, int hi) { return pack_bf16(__int2float_rn(lo), __int2float_rn(hi)); }
DEVINL float ex2(float x) { float y; asm("ex2.approx.ftz.f32 %0, %1;" : "=f"(y) : "f"(x)); return y; }
DEVINL uint32_t ldg32(const void* p) { uint32_t v; asm volatile("ld.global.nc.u32 %0, [%1];" : "=r"(v) : "l"(p)); return v; }
DEVINL uint4 lds128(uint32_t a) { uint4 v; asm volatile("ld.shared.v4.u32 {%0,%1,%2,%3}, [%4];" : "=r"(v.x), "=r"(v.y), "=r"(v.z), "=r"(v.w) : "r"(a) : "memory"); return v; }
DEVINL uint2 lds64(uint32_t a) { uint2 v; asm volatile("ld.shared.v2.u32 {%0,%1}, [%2];" : "=r"(v.x), "=r"(v.y) : "r"(a) : "memory"); return v; }
DEVINL uint32_t lds32(uint32_t a) { uint32_t v; asm volatile("ld.shared.u32 %0, [%1];" : "=r"(v) : "r"(a) : "memory"); return v; }
DEVINL void sts128(uint32_t a, uint4 v) { asm volatile("st.shared.v4.u32 [%0], {%1,%2,%3,%4};" ::"r"(a), "r"(v.x), "r"(v.y), "r"(v.z), "r"(v.w) : "memory"); }
DEVINL void sts64(uint32_t a, uint32_t x, uint32_t y) { asm volatile("st.shared.v2.u32 [%0], {%1,%2};" ::"r"(a), "r"(x), "r"(y) : "memory"); }

struct Params {
  const __nv_bfloat16* q; const int* qk; const __nv_bfloat16* ks; const __nv_bfloat16* kz;
  const int* qv; const __nv_bfloat16* vs; const __nv_bfloat16* vz;
  const __nv_bfloat16* qc; const __nv_bfloat16* qs; const __nv_bfloat16* kc; const __nv_bfloat16* ksn;
  __nv_bfloat16* out;
  uint8_t* gK; uint8_t* gV; unsigned* flags;
};

constexpr int SM_Q = 0;
constexpr int SM_K = SM_Q + TILE_BYTES;
constexpr int SM_V = SM_K + KST * TILE_BYTES;
constexpr int RSLOT = 12288;
constexpr int SM_R = SM_V + VST * TILE_BYTES;
constexpr int SM_T = SM_R + 2 * RSLOT;
constexpr int SM_BAR = SM_T + 17 * 128;
constexpr int SM_TOTAL = SM_BAR + 512;
static_assert(SM_TOTAL <= 232448, "smem");

DEVINL void kraw_issue(const Params& p, int h, int slot, int j, uint32_t dst, uint32_t bar) {
  const int row = j * 128 + slot * 8;
  bulk_load(dst, p.qk + ((size_t)h * S + row) * D, 4096, bar);
  bulk_load(dst + 4096, p.kc + (size_t)row * D, 2048, bar);
  bulk_load(dst + 6144, p.ksn + (size_t)row * D, 2048, bar);
}
DEVINL void vraw_issue(const Params& p, int h, int slot, int j, uint32_t dst, uint32_t bar) {
  bulk_load(dst + 8192, p.qv + ((size_t)h * S + j * 128 + slot * 8) * D, 4096, bar);
}
DEVINL void step_issue(const Params& p, int h, int slot, int j, uint32_t sbase, uint32_t rfull) {
  const uint32_t dst = sbase + SM_R + (j & 1) * RSLOT, bar = rfull + 8 * (j & 1);
  mbar_expect_tx(bar, j < NT ? RSLOT : 4096);
  if (j < NT) kraw_issue(p, h, slot, j, dst, bar);
  vraw_issue(p, h, slot, j - 1, dst, bar);
}
DEVINL void step_prefetch(const Params& p, int h, int slot, int j) {
  const int row = j * 128 + slot * 8;
  prefetch_l2(p.qk + ((size_t)h * S + row) * D, 4096);
  prefetch_l2(p.qv + ((size_t)h * S + row - 128) * D, 4096);
  if (h == (j & 7)) { prefetch_l2(p.kc + (size_t)row * D, 2048); prefetch_l2(p.ksn + (size_t)row * D, 2048); }
}
DEVINL void qraw_issue(const Params& p, int h, int slot, int cw, uint32_t sbase, uint32_t bar) {
  const int row = slot * 128 + cw * 16;
  const uint32_t qa = sbase + SM_Q + (cw >> 2) * 16384 + (cw & 3) * 2048;
  const __nv_bfloat16* q = p.q + ((size_t)h * S + row) * D;
  mbar_expect_tx(bar, 3 * 4096);
  bulk_load(qa, q, 2048, bar);
  bulk_load(qa + 8192, q + 8 * D, 2048, bar);
  bulk_load(sbase + SM_V + 1 * TILE_BYTES + cw * 4096, p.qc + (size_t)row * D, 4096, bar);
  bulk_load(sbase + SM_V + 2 * TILE_BYTES + cw * 4096, p.qs + (size_t)row * D, 4096, bar);
}

DEVINL void kprep_unit(uint32_t a, uint32_t ca, uint32_t sc, uint32_t zp, uint8_t* dst) {
  const uint4 A = lds128(a), B = lds128(a + 256);
  const uint2 cl = lds64(ca), ch = lds64(ca + 128), sl = lds64(ca + 2048), sh = lds64(ca + 2048 + 128);
  const uint32_t l0 = bmul(bsub(i2bf2(A.x, A.y), dup_lo(zp)), dup_lo(sc)), l1 = bmul(bsub(i2bf2(A.z, A.w), dup_lo(zp)), dup_lo(sc));
  const uint32_t h0 = bmul(bsub(i2bf2(B.x, B.y), dup_hi(zp)), dup_hi(sc)), h1 = bmul(bsub(i2bf2(B.z, B.w), dup_hi(zp)), dup_hi(sc));
  uint2 olo, ohi;
  olo.x = bsub(bmul(l0, cl.x), bmul(h0, sl.x));
  olo.y = bsub(bmul(l1, cl.y), bmul(h1, sl.y));
  ohi.x = badd(bmul(h0, ch.x), bmul(l0, sh.x));
  ohi.y = badd(bmul(h1, ch.y), bmul(l1, sh.y));
  *(uint2*)dst = olo;
  *(uint2*)(dst + 16384) = ohi;
}
DEVINL void vprep_unit(uint32_t a, uint32_t sc, uint32_t zp, uint8_t* dst) {
  const uint2 x0 = lds64(a), x1 = lds64(a + 32), y0 = lds64(a + 256), y1 = lds64(a + 288);
  uint2 olo, ohi;
  olo.x = bmul(bsub(i2bf2(x0.x, x0.y), dup_lo(zp)), dup_lo(sc)); olo.y = bmul(bsub(i2bf2(x1.x, x1.y), dup_lo(zp)), dup_lo(sc));
  ohi.x = bmul(bsub(i2bf2(y0.x, y0.y), dup_hi(zp)), dup_hi(sc)); ohi.y = bmul(bsub(i2bf2(y1.x, y1.y), dup_hi(zp)), dup_hi(sc));
  *(uint2*)dst = olo;
  *(uint2*)(dst + 16384) = ohi;
}

__global__ void __launch_bounds__(NTHREADS, 1) __cluster_dims__(2, 1, 1)
attn_kernel(const __grid_constant__ Params p) {
  extern __shared__ __align__(1024) uint8_t smem_raw[];
  const uint32_t sbase = smem_u32(smem_raw);
  const int tid = threadIdx.x, lane = tid & 31;
  const int warp = __shfl_sync(0xffffffffu, tid >> 5, 0);
  const int h = blockIdx.x >> 4, slot = blockIdx.x & 15;
  const uint32_t rank = blockIdx.x & 1;
  const uint32_t kfull = sbase + SM_BAR, kempty = kfull + 8 * KST, vfull = kempty + 8 * KST, vempty = vfull + 8 * VST;
  const uint32_t rfull = vempty + 8 * VST, qfull = rfull + 16, done = qfull + 64, tick = done + 8 * 17, redo = tick + 8 * 16;

  if (warp == 13) {
    if (elect_one()) {
      mbar_init(rfull, 1); mbar_init(rfull + 8, 1);
      asm volatile("fence.mbarrier_init.release.cluster;" ::: "memory");
      asm volatile("fence.proxy.async.shared::cta;" ::: "memory");
      mbar_expect_tx(rfull, RSLOT);
      kraw_issue(p, h, slot, 0, sbase + SM_R, rfull);
      mbar_expect_tx(rfull + 8, 8192);
      kraw_issue(p, h, slot, 1, sbase + SM_R + RSLOT, rfull + 8);
      vraw_issue(p, h, slot, 0, sbase + SM_R, rfull);
    }
  }
  if (warp == 12) {
    if (elect_one()) {
#pragma unroll
      for (int i = 0; i < KST; i++) { mbar_init(kfull + 8 * i, 1); mbar_init(kempty + 8 * i, 4); }
#pragma unroll
      for (int i = 0; i < VST; i++) { mbar_init(vfull + 8 * i, 1); mbar_init(vempty + 8 * i, 4); }
#pragma unroll
      for (int i = 0; i < 8; i++) mbar_init(qfull + 8 * i, 1);
      asm volatile("st.shared.u32 [%0], %1;" ::"r"(redo), "r"(0) : "memory");
      asm volatile("fence.mbarrier_init.release.cluster;" ::: "memory");
      asm volatile("fence.release.sync_restrict::shared::cta.cluster;" ::: "memory");
    }
  }
  if (warp == 8 || warp == 9) {
    if (elect_one()) {
#pragma unroll
      for (int i = 0; i < 16; i++) mbar_init((warp == 8 ? done + 8 : tick) + 8 * i, warp == 8 ? 4 : 1);
      asm volatile("fence.mbarrier_init.release.cluster;" ::: "memory");
    }
  }
  __syncwarp();
  cluster_sync();

  if (tid < 256) {
    const int j = (tid >> 3) & 15, r = tid & 7, isv = tid >> 7;
    const size_t o = ((size_t)h * S + j * 128 + slot * 8 + r) * 2;
    const uint32_t sc = ldg32((isv ? p.vs : p.ks) + o), zp = ldg32((isv ? p.vz : p.kz) + o);
    sts64(sbase + SM_T + (j + isv) * 128 + r * 16 + isv * 8, sc, zp);
  }
  const int r8 = (warp & 3) * 2 + (lane >> 4), pm = lane & 15;
  const uint32_t dofs = (uint32_t)(h * NT * TILE_BYTES + (slot * 8 + r8) * 128 + (((pm >> 1) ^ r8) << 4) + (pm & 1) * 8);
  const uint32_t ka = sbase + SM_R + r8 * 512 + pm * 16, kca = sbase + SM_R + 4096 + r8 * 256 + pm * 8;
  const uint32_t va = sbase + SM_R + 8192 + r8 * 512 + (pm >> 3) * 128 + (pm & 1) * 64 + ((pm >> 1) & 3) * 8;
  const uint32_t ta = sbase + SM_T + r8 * 16;
  if (warp < 12) {
    bar_sync(7, 12 * 32);
    const int e = warp >> 2;
    mbar_wait(rfull + 8 * (e & 1), 0);
    if (e < 2) {
      const uint2 t = lds64(ta + e * 128);
      kprep_unit(ka + e * RSLOT, kca + e * RSLOT, t.x, t.y, p.gK + dofs + e * TILE_BYTES);
    } else {
      const uint2 t = lds64(ta + 128 + 8);
      vprep_unit(va, t.x, t.y, p.gV + dofs);
    }
    bar_arrive(6, 13 * 32);
  }

  if (warp >= 12) {
    asm volatile("setmaxnreg.dec.sync.aligned.u32 " STR(LREG) ";");
    if (warp == 12) {
      const unsigned* fl = p.flags + (h * 32 + lane) * FSTR;
      unsigned base;
      asm volatile("ld.relaxed.gpu.global.u32 %0, [%1];" : "=r"(base) : "l"(p.flags + h * 32 * FSTR) : "memory");
      const uint8_t* srcK = p.gK + (size_t)h * NT * TILE_BYTES + rank * 16384;
      const uint8_t* srcV = p.gV + (size_t)h * NT * TILE_BYTES + rank * 16384;
      const uint32_t dK = sbase + SM_K + rank * 16384, dV = sbase + SM_V + rank * 16384;
      const unsigned target = (base / FLAG_INC + 1) * FLAG_INC;
      unsigned ready = 0;
      auto need = [&](int f) {
        if ((ready >> f) & 1) return;
        int it = 0;
        do {
          unsigned v = target - 1;
          if ((unsigned)(lane - f) < FWIN) asm volatile("ld.relaxed.gpu.global.u32 %0, [%1];" : "=r"(v) : "l"(fl) : "memory");
          ready = __ballot_sync(0xffffffffu, (int)(v - target) >= 0);
        } while (!((ready >> f) & 1) && ++it < 4 * SPIN_LIMIT);
        asm volatile("fence.acquire.gpu;" ::: "memory");
        __syncwarp();
      };
      bar_sync(6, 13 * 32);
      asm volatile("fence.proxy.async.global;" ::: "memory");
      asm volatile("fence.release.gpu;" ::: "memory");
      if (lane == 0) asm volatile("red.relaxed.gpu.global.add.u32 [%0], 1;" ::"l"(fl) : "memory");
      if (elect_one()) {
        step_issue(p, h, slot, 2, sbase, rfull);
#pragma unroll
        for (int i = NDIR; i < 8; i++) qraw_issue(p, h, slot, i, sbase, qfull + 8 * i);
      }
      need(0);
      if (elect_one()) {
        mbar_expect_tx(kfull, TILE_BYTES);
#pragma unroll
        for (int i = 0; i < 4; i++) bulk_load_mc(dK + i * 4096, srcK + i * 4096, 4096, kfull, (uint16_t)3);
        step_issue(p, h, slot, 3, sbase, rfull);
        mbar_wait(kfull, 0);
        mbar_expect_tx(kfull + 8, TILE_BYTES);
        bulk_load_mc(dK + TILE_BYTES, srcK + TILE_BYTES, 16384, kfull + 8, (uint16_t)3);
        mbar_expect_tx(vfull, TILE_BYTES);
        bulk_load_mc(dV, srcV, 16384, vfull, (uint16_t)3);
        mbar_arrive(tick + 8);
      }
      int kst = 0, vst = 1;
      uint32_t kpar = 0, vpar = 0;
      int j = 2;
#pragma unroll 1
      for (int pass = 0; pass < 2; pass++) {
#pragma unroll 1
        for (; j <= NT; j++) {
          if (pass == 0) need(j);
          if (elect_one()) {
            if (j < NT) {
              mbar_wait(kempty + 8 * kst, (kpar >> kst) & 1);
              mbar_expect_tx(kfull + 8 * kst, TILE_BYTES);
              bulk_load_mc(dK + kst * TILE_BYTES, srcK + j * TILE_BYTES, 16384, kfull + 8 * kst, (uint16_t)3);
              if (pass == 0) mbar_arrive(tick + 8 * j);
            }
            if (j > 0) {
              mbar_wait(vempty + 8 * vst, (vpar >> vst) & 1);
              mbar_expect_tx(vfull + 8 * vst, TILE_BYTES);
              bulk_load_mc(dV + vst * TILE_BYTES, srcV + (j - 1) * TILE_BYTES, 16384, vfull + 8 * vst, (uint16_t)3);
            }
          }
          if (j < NT) { kpar ^= 1u << kst; if (++kst == KST) kst = 0; }
          if (j > 0) { vpar ^= 1u << vst; if (++vst == VST) vst = 0; }
        }
        __syncwarp();
        cluster_sync();
        if (pass == 1 || lds32(redo) == 0) break;
        j = 0;
      }
    } else {
      if (warp == 13) {
        if (elect_one()) {
#pragma unroll 1
          for (int i = 0; i < NDIR; i++) qraw_issue(p, h, slot, i, sbase, qfull + 8 * i);
        }
        mbar_wait(qfull + 8 * PF2AT, 0);
        if (elect_one()) step_prefetch(p, h, slot, 2);
#pragma unroll 1
        for (int j = 4; j <= NT; j++) {
          mbar_wait(tick + 8 * (j - LEAD), 0);
          mbar_wait(done + 8 * (j - 2), 0);
          if (elect_one()) {
            step_issue(p, h, slot, j, sbase, rfull);
          }
        }
      } else {
#pragma unroll 1
        for (int j = 2 + (warp & 1); j <= NT; j += 2) {
          mbar_wait(done + 8 * j, 0);
          if (elect_one()) {
            asm volatile("fence.proxy.async.global;" ::: "memory");
            asm volatile("red.release.gpu.global.add.u32 [%0], 1;" ::"l"(p.flags + (h * 32 + j) * FSTR) : "memory");
          }
          __syncwarp();
        }
      }
      cluster_sync();
      if (lds32(redo) != 0) cluster_sync();
    }
  } else if (warp >= 8) {
    asm volatile("setmaxnreg.dec.sync.aligned.u32 " STR(PREG) ";");
    mbar_wait(rfull + 8, 0);
    uint8_t* gk = p.gK + dofs + 2 * TILE_BYTES;
    uint8_t* gv = p.gV + dofs + TILE_BYTES;
    uint32_t tj = ta + 2 * 128, dn = done + 16, par = 1;
#pragma unroll 1
    for (int j = 2; j < NT; j += 2) {
#pragma unroll
      for (int u = 0; u < 2; u++) {
        mbar_wait(rfull + 8 * u, par);
        const uint4 t = lds128(tj + u * 128);
        kprep_unit(ka + u * RSLOT, kca + u * RSLOT, t.x, t.y, gk + u * TILE_BYTES);
        vprep_unit(va + u * RSLOT, t.z, t.w, gv + u * TILE_BYTES);
        __syncwarp();
        if (lane == 0) mbar_arrive(dn + 8 * u);
      }
      gk += 2 * TILE_BYTES; gv += 2 * TILE_BYTES; tj += 256; dn += 16; par ^= 1;
    }
    mbar_wait(rfull, par);
    const uint4 t = lds128(tj);
    vprep_unit(va, t.z, t.w, gv);
    __syncwarp();
    if (lane == 0) mbar_arrive(dn);
    cluster_sync();
    if (lds32(redo) != 0) cluster_sync();
  } else {
    asm volatile("setmaxnreg.inc.sync.aligned.u32 " STR(CREG) ";");
    const int w = warp >> 2, wq = warp & 3;
    const int g = lane >> 2, c = lane & 3;
    const bool sig = (wq == 0) && (lane < 2);
    if (w == 1) bar_arrive(1, 256);
    {
      const int rr = lane >> 3, m = lane & 7;
      const uint32_t qa = sbase + SM_Q + w * 16384 + wq * 2048;
      const uint32_t ro = rr * 256 + m * 16;
      const uint32_t ca = sbase + SM_V + 1 * TILE_BYTES + warp * 4096 + ro;
      uint4 olo[4], ohi[4];
      mbar_wait(qfull + 8 * warp, 0);
#pragma unroll
      for (int i = 0; i < 4; i++) {
        const uint32_t qo = qa + (i >> 1) * 8192 + (i & 1) * 1024 + ro;
        const uint4 ql = lds128(qo), qh = lds128(qo + 128);
        const uint4 cl = lds128(ca + i * 1024), ch = lds128(ca + i * 1024 + 128);
        const uint4 sl = lds128(ca + TILE_BYTES + i * 1024), sh = lds128(ca + TILE_BYTES + i * 1024 + 128);
        olo[i].x = bscale(bsub(bmul(ql.x, cl.x), bmul(qh.x, sl.x)));
        olo[i].y = bscale(bsub(bmul(ql.y, cl.y), bmul(qh.y, sl.y)));
        olo[i].z = bscale(bsub(bmul(ql.z, cl.z), bmul(qh.z, sl.z)));
        olo[i].w = bscale(bsub(bmul(ql.w, cl.w), bmul(qh.w, sl.w)));
        ohi[i].x = bscale(badd(bmul(qh.x, ch.x), bmul(ql.x, sh.x)));
        ohi[i].y = bscale(badd(bmul(qh.y, ch.y), bmul(ql.y, sh.y)));
        ohi[i].z = bscale(badd(bmul(qh.z, ch.z), bmul(ql.z, sh.z)));
        ohi[i].w = bscale(badd(bmul(qh.w, ch.w), bmul(ql.w, sh.w)));
      }
      __syncwarp();
#pragma unroll
      for (int i = 0; i < 4; i++) {
        const int r = rr + 4 * i;
        const uint32_t dst = qa + r * 128 + ((m ^ (r & 7)) << 4);
        sts128(dst, olo[i]);
        sts128(dst + 8192, ohi[i]);
      }
      asm volatile("fence.proxy.async.shared::cta;" ::: "memory");
    }
    bar_sync(3 + w, 128);
    if (sig) { mbar_arrive_remote(vempty + 8, lane); mbar_arrive_remote(vempty + 16, lane); }

    const uint64_t qdesc = mkdesc(sbase + SM_Q + w * 16384, 16, 1024);
    const uint64_t kdesc0 = mkdesc(sbase + SM_K, 16, 1024);
    const uint64_t vdesc0 = mkdesc(sbase + SM_V, 16384, 1024);

    float sacc[64], oacc[64];
    uint32_t pa[32];
    int kst = 0, kph = 0, vst = 0, vph = 0, vrel = 0;

    auto issue_qk = [&](int st) {
      const uint64_t kd = kdesc0 + (uint64_t)(st * (TILE_BYTES >> 4));
#pragma unroll
      for (int k = 0; k < 8; k++) {
        const uint64_t off = (uint64_t)(((k >> 2) * 16384 + (k & 3) * 32) >> 4);
        const uint64_t qoff = (uint64_t)(((k >> 2) * 8192 + (k & 3) * 32) >> 4);
        if (k == 0) wgmma_ss_first(sacc, qdesc + qoff, kd + off);
        else wgmma_ss(sacc, qdesc + qoff, kd + off);
      }
      wg_commit();
    };
    auto issue_pv = [&](int st) {
      const uint64_t vd = vdesc0 + (uint64_t)(st * (TILE_BYTES >> 4));
#pragma unroll
      for (int k = 0; k < 8; k++)
        wgmma_rs_tb(oacc, pa[4 * k], pa[4 * k + 1], pa[4 * k + 2], pa[4 * k + 3], vd + (uint64_t)(k * (2048 >> 4)));
      wg_commit();
    };
    auto next_k = [&]() { if (++kst == KST) { kst = 0; kph ^= 1; } };
    auto next_v = [&]() { vrel = vst; if (++vst == VST) { vst = 0; vph ^= 1; } };
    __nv_bfloat16* optr = p.out + ((size_t)h * S + slot * 128 + w * 64 + wq * 16 + g) * D + c * 8;
    auto store_half = [&](const float* o, int hf, float i0, float i1, uint32_t& mx0, uint32_t& mx1) {
      __nv_bfloat16* o0 = optr + hf * 64;
      __nv_bfloat16* o1 = o0 + 8 * D;
#pragma unroll
      for (int b = 0; b < 2; b++) {
        uint4 u, v;
        u.x = pack_bf16(o[16 * b + 0] * i0, o[16 * b + 1] * i0);
        u.y = pack_bf16(o[16 * b + 4] * i0, o[16 * b + 5] * i0);
        u.z = pack_bf16(o[16 * b + 8] * i0, o[16 * b + 9] * i0);
        u.w = pack_bf16(o[16 * b + 12] * i0, o[16 * b + 13] * i0);
        v.x = pack_bf16(o[16 * b + 2] * i1, o[16 * b + 3] * i1);
        v.y = pack_bf16(o[16 * b + 6] * i1, o[16 * b + 7] * i1);
        v.z = pack_bf16(o[16 * b + 10] * i1, o[16 * b + 11] * i1);
        v.w = pack_bf16(o[16 * b + 14] * i1, o[16 * b + 15] * i1);
        *(uint4*)(o0 + 32 * b) = u;
        *(uint4*)(o1 + 32 * b) = v;
        mx0 = bmaxabs(bmaxabs(mx0, u.x), bmaxabs(u.y, bmaxabs(u.z, u.w)));
        mx1 = bmaxabs(bmaxabs(mx1, v.x), bmaxabs(v.y, bmaxabs(v.z, v.w)));
      }
    };

    {
      float l0 = 0.f, l1 = 0.f, l2 = 0.f, l3 = 0.f;
#pragma unroll
      for (int i = 0; i < 64; i++) oacc[i] = 0.f;
      pin(oacc);
      asm volatile("" : "+l"(optr));
      {
        float sa[32], sb[32];
        auto exp_half = [&](float (&x)[32], int o) {
#pragma unroll
          for (int i = 0; i < 8; i++) {
            const float e0 = ex2(x[4 * i]), e1 = ex2(x[4 * i + 1]), e2 = ex2(x[4 * i + 2]), e3 = ex2(x[4 * i + 3]);
            l0 += e0; l1 += e1; l2 += e2; l3 += e3;
            pa[o + 2 * i] = pack_bf16(e0, e1); pa[o + 2 * i + 1] = pack_bf16(e2, e3);
          }
        };
        mbar_wait(kfull, 0);
        bar_sync(1 + w, 256);
        wg_fence();
#pragma unroll
        for (int k = 0; k < 8; k++) {
          const uint64_t off = (uint64_t)(((k >> 2) * 16384 + (k & 3) * 32) >> 4), qoff = (uint64_t)(((k >> 2) * 8192 + (k & 3) * 32) >> 4);
          if (k == 0) wgmma_ss_first(sa, qdesc + qoff, kdesc0 + off); else wgmma_ss(sa, qdesc + qoff, kdesc0 + off);
        }
        wg_commit();
#pragma unroll
        for (int k = 0; k < 8; k++) {
          const uint64_t off = (uint64_t)(((k >> 2) * 16384 + (k & 3) * 32 + 8192) >> 4), qoff = (uint64_t)(((k >> 2) * 8192 + (k & 3) * 32) >> 4);
          if (k == 0) wgmma_ss_first(sb, qdesc + qoff, kdesc0 + off); else wgmma_ss(sb, qdesc + qoff, kdesc0 + off);
        }
        wg_commit();
        bar_arrive(1 + (w ^ 1), 256);
        wg_wait<1>();
        pin(sa);
        exp_half(sa, 0);
        mbar_wait(kfull, 0);
        wg_wait<0>();
        pin(sb);
        if (sig) mbar_arrive_remote(kempty, lane);
        exp_half(sb, 16);
        next_k();
        mbar_wait(kfull + 8, 0);
      }
#pragma unroll 1
      for (int j = 0; j < NT - 1; j++) {
        bar_sync(1 + w, 256);
        pin(pa); pin(oacc);
        wg_fence();
        issue_qk(kst);
        mbar_wait(vfull + 8 * vst, vph);
        wg_fence();
        issue_pv(vst);
        bar_arrive(1 + (w ^ 1), 256);
        wg_wait<1>();
        pin(sacc);
        if (sig && j + 1 < NT - KST) mbar_arrive_remote(kempty + 8 * kst, lane);
#pragma unroll
        for (int i = 0; i < 16; i++) {
          sacc[4 * i] = ex2(sacc[4 * i]); sacc[4 * i + 1] = ex2(sacc[4 * i + 1]);
          sacc[4 * i + 2] = ex2(sacc[4 * i + 2]); sacc[4 * i + 3] = ex2(sacc[4 * i + 3]);
          l0 += sacc[4 * i]; l1 += sacc[4 * i + 1]; l2 += sacc[4 * i + 2]; l3 += sacc[4 * i + 3];
        }
        next_k(); next_v();
        mbar_wait(kfull + 8 * kst, kph ^ (j == NT - 2));
        wg_wait<0>();
        pin(pa); pin(sacc);
        if (sig && j < NT - VST) mbar_arrive_remote(vempty + 8 * vrel, lane);
#pragma unroll
        for (int i = 0; i < 32; i++) pa[i] = pack_bf16(sacc[2 * i], sacc[2 * i + 1]);
      }
      mbar_wait(vfull + 8 * vst, vph);
      float oa[32], ob[32];
      pin(oacc);
#pragma unroll
      for (int i = 0; i < 32; i++) {
        asm volatile("mov.b32 %0, %1;" : "=f"(oa[i]) : "f"(oacc[i]));
        asm volatile("mov.b32 %0, %1;" : "=f"(ob[i]) : "f"(oacc[32 + i]));
      }
      bar_sync(1 + w, 256);
      pin(pa); pin(oa); pin(ob);
      wg_fence();
      {
        const uint64_t vd = vdesc0 + (uint64_t)(vst * (TILE_BYTES >> 4));
#pragma unroll
        for (int k = 0; k < 8; k++) wgmma_rs_tb(oa, pa[4 * k], pa[4 * k + 1], pa[4 * k + 2], pa[4 * k + 3], vd + (uint64_t)(k * (2048 >> 4)));
        wg_commit();
#pragma unroll
        for (int k = 0; k < 8; k++) wgmma_rs_tb(ob, pa[4 * k], pa[4 * k + 1], pa[4 * k + 2], pa[4 * k + 3], vd + (uint64_t)((16384 + k * 2048) >> 4));
        wg_commit();
      }
      bar_arrive(w ? 9 : 2, w ? 128 : 256);
      mbar_wait(vfull + 8 * vst, vph);
      l0 += l1; l2 += l3;
      l0 += __shfl_xor_sync(0xffffffffu, l0, 1); l2 += __shfl_xor_sync(0xffffffffu, l2, 1);
      l0 += __shfl_xor_sync(0xffffffffu, l0, 2); l2 += __shfl_xor_sync(0xffffffffu, l2, 2);
      float i0, i1;
      asm volatile("rcp.approx.ftz.f32 %0, %1;" : "=f"(i0) : "f"(l0));
      asm volatile("rcp.approx.ftz.f32 %0, %1;" : "=f"(i1) : "f"(l2));
      uint32_t mx0 = 0, mx1 = 0;
      wg_wait<1>();
      pin(oa);
      store_half(oa, 0, i0, i1, mx0, mx1);
      mbar_wait(vfull + 8 * vst, vph);
      wg_wait<0>();
      pin(ob);
      next_v();
      store_half(ob, 1, i0, i1, mx0, mx1);
      const float a0 = fmaxf(fabsf(__uint_as_float(mx0 << 16)), fabsf(__uint_as_float(mx0 & 0xffff0000u)));
      const float a1 = fmaxf(fabsf(__uint_as_float(mx1 << 16)), fabsf(__uint_as_float(mx1 & 0xffff0000u)));
      const bool nan = ((mx0 & 0x7f80u) == 0x7f80u) | ((mx0 & 0x7f800000u) == 0x7f800000u) |
                       ((mx1 & 0x7f80u) == 0x7f80u) | ((mx1 & 0x7f800000u) == 0x7f800000u);
      const bool ok = !nan && l0 >= 0x1p-64f && l0 <= 0x1p64f && l2 >= 0x1p-64f && l2 <= 0x1p64f &&
                      a0 * l0 >= 0x1p-90f && a1 * l2 >= 0x1p-90f;
      if (!ok) {
        asm volatile("{\n.reg .b32 ra;\nmapa.shared::cluster.u32 ra, %0, 0;\nst.shared::cluster.u32 [ra], 1;\n"
                     "mapa.shared::cluster.u32 ra, %0, 1;\nst.shared::cluster.u32 [ra], 1;\nfence.acq_rel.cluster;\n}" ::"r"(redo) : "memory");
      }
    }
    __syncwarp();
    cluster_sync();
    if (lds32(redo) != 0) {
      if (sig) {
#pragma unroll
        for (int i = 0; i < KST; i++) mbar_arrive_remote(kempty + 8 * i, lane);
#pragma unroll
        for (int i = 0; i < VST; i++) mbar_arrive_remote(vempty + 8 * i, lane);
      }
      float m0 = -INFINITY, m1 = -INFINITY, l0 = 0.f, l1 = 0.f;
#pragma unroll
      for (int i = 0; i < 64; i++) oacc[i] = 0.f;
#pragma unroll 1
      for (int j = 0; j < NT; j++) {
        mbar_wait(kfull + 8 * kst, kph);
        wg_fence();
        issue_qk(kst);
        wg_wait<0>();
        pin(sacc);
        if (sig && j < NT - KST) mbar_arrive_remote(kempty + 8 * kst, lane);
        next_k();
        float n0 = fmaxf(sacc[0], sacc[1]), n1 = fmaxf(sacc[2], sacc[3]);
#pragma unroll
        for (int i = 1; i < 16; i++) {
          n0 = fmaxf(n0, fmaxf(sacc[4 * i], sacc[4 * i + 1]));
          n1 = fmaxf(n1, fmaxf(sacc[4 * i + 2], sacc[4 * i + 3]));
        }
        n0 = fmaxf(n0, __shfl_xor_sync(0xffffffffu, n0, 1));
        n1 = fmaxf(n1, __shfl_xor_sync(0xffffffffu, n1, 1));
        n0 = fmaxf(n0, __shfl_xor_sync(0xffffffffu, n0, 2));
        n1 = fmaxf(n1, __shfl_xor_sync(0xffffffffu, n1, 2));
        n0 = fmaxf(n0, m0); n1 = fmaxf(n1, m1);
        const float sc0 = ex2(m0 - n0), sc1 = ex2(m1 - n1);
        m0 = n0; m1 = n1;
        l0 *= sc0; l1 *= sc1;
#pragma unroll
        for (int i = 0; i < 16; i++) {
          const float e0 = ex2(sacc[4 * i] - m0), e1 = ex2(sacc[4 * i + 1] - m0);
          const float e2 = ex2(sacc[4 * i + 2] - m1), e3 = ex2(sacc[4 * i + 3] - m1);
          l0 += e0 + e1; l1 += e2 + e3;
          pa[2 * i] = pack_bf16(e0, e1); pa[2 * i + 1] = pack_bf16(e2, e3);
          oacc[4 * i] *= sc0; oacc[4 * i + 1] *= sc0; oacc[4 * i + 2] *= sc1; oacc[4 * i + 3] *= sc1;
        }
        mbar_wait(vfull + 8 * vst, vph);
        pin(pa); pin(oacc);
        wg_fence();
        issue_pv(vst);
        wg_wait<0>();
        pin(oacc); pin(pa);
        if (sig && j < NT - VST) mbar_arrive_remote(vempty + 8 * vst, lane);
        next_v();
      }
      l0 += __shfl_xor_sync(0xffffffffu, l0, 1); l1 += __shfl_xor_sync(0xffffffffu, l1, 1);
      l0 += __shfl_xor_sync(0xffffffffu, l0, 2); l1 += __shfl_xor_sync(0xffffffffu, l1, 2);
      uint32_t mx0 = 0, mx1 = 0;
      store_half(oacc, 0, 1.0f / l0, 1.0f / l1, mx0, mx1);
      store_half(oacc + 32, 1, 1.0f / l0, 1.0f / l1, mx0, mx1);
      cluster_sync();
    }
  }
}

extern "C" void kernel_launch(void* const* d_in, const int* in_sizes, int n_in, void* d_out, int out_size) {
  static bool init = false;
  static void *aK, *aV, *aF;
  if (!init) {
    cudaGetSymbolAddress(&aK, g_K); cudaGetSymbolAddress(&aV, g_V); cudaGetSymbolAddress(&aF, g_flags);
    cudaFuncSetAttribute(attn_kernel, cudaFuncAttributeMaxDynamicSharedMemorySize, SM_TOTAL);
    init = true;
  }
  Params p;
  p.q = (const __nv_bfloat16*)d_in[0]; p.qk = (const int*)d_in[1];
  p.ks = (const __nv_bfloat16*)d_in[2]; p.kz = (const __nv_bfloat16*)d_in[3];
  p.qv = (const int*)d_in[4]; p.vs = (const __nv_bfloat16*)d_in[5]; p.vz = (const __nv_bfloat16*)d_in[6];
  p.qc = (const __nv_bfloat16*)d_in[7]; p.qs = (const __nv_bfloat16*)d_in[8];
  p.kc = (const __nv_bfloat16*)d_in[9]; p.ksn = (const __nv_bfloat16*)d_in[10];
  p.out = (__nv_bfloat16*)d_out;
  p.gK = (uint8_t*)aK; p.gV = (uint8_t*)aV; p.flags = (unsigned*)aF;
  attn_kernel<<<H * NT, NTHREADS, SM_TOTAL, cudaStreamPerThread>>>(p);
}
```
